```python
import torch

def _softmax(x, axis=-1):
    return torch.softmax(x, dim=axis)
def _gelu(x):
    return torch.nn.functional.gelu(x, approximate="tanh")
def _silu(x):
    return torch.nn.functional.silu(x)
def _sigmoid(x):
    return torch.sigmoid(x)
def _layernorm(x, axis=-1, eps=1e-5):
    m = x.mean(dim=axis, keepdim=True)
    v = x.var(dim=axis, keepdim=True, unbiased=False)
    return (x - m) / torch.sqrt(v + eps)
def _scatter_add(tgt, idx, src, axis=0):
    return tgt.clone().index_add_(axis, idx, src)
def _segment_sum(src, seg, n):
    out = torch.zeros((n,) + src.shape[1:], dtype=src.dtype)
    return out.index_add_(0, seg, src)
def _pad(x, pw):
    flat = tuple(v for pair in reversed(pw) for v in pair)
    return torch.nn.functional.pad(x, flat)

kernel_name = 'gated_mix__sliding_block__softmax_full_mha__prompt'

def setup_inputs():

    _w = (lambda a: (lambda t: t.to(torch.bfloat16) if t.is_floating_point() else t)(torch.as_tensor(a)))
    def _A_setup():
        B, S, D = 1, 2048, 512
        return {
            "x": _w((lambda *s: torch.randn(*s, dtype=torch.bfloat16) * 0.05)(B, S, D)),
            "wqkv": _w((lambda *s: torch.randn(*s, dtype=torch.bfloat16) * 1.6)(D, 3 * D)),
            "wo": _w((lambda *s: torch.randn(*s, dtype=torch.bfloat16) * 0.05)(D, D)),
        }
    _A_in = _A_setup()

    def _B_setup():
        B, S, D = 1, 2048, 512
        return {
            "x": _w((lambda *s: torch.randn(*s, dtype=torch.bfloat16) * 0.05)(B, S, D)),
            "wqkv": _w((lambda *s: torch.randn(*s, dtype=torch.bfloat16) * 1.6)(D, 3 * D)),
            "wo": _w((lambda *s: torch.randn(*s, dtype=torch.bfloat16) * 0.1)(D, D)),
        }
    _B_in = _B_setup()

    return {
        "A_x": _A_in["x"],
        "A_wqkv": _A_in["wqkv"],
        "A_wo": _A_in["wo"],
        "B_x": _B_in["x"],
        "B_wqkv": _B_in["wqkv"],
        "B_wo": _B_in["wo"],
        "gate_w": _w((lambda *s: torch.randn(*s, dtype=torch.bfloat16) * 0.05)(512) * 16.0),
    }

def reference(A_x, A_wqkv, A_wo, B_x, B_wqkv, B_wo, gate_w):
    def _A_ref(x, wqkv, wo):
        B, S, D = x.shape
        H = 32; Dh = D // H; W = 256
        qkv = (lambda x, *d: x.permute(*d))((x @ wqkv).reshape(B, S, 3, H, Dh), 2, 0, 3, 1, 4)
        q, k, v = qkv[0], qkv[1], qkv[2]
        scores = torch.einsum("bhqd,bhkd->bhqk", q, k) * (Dh ** -0.5)
        idx = torch.arange(S)
        mask = (idx[:, None] - idx[None, :] >= 0) & (idx[:, None] - idx[None, :] < W)
        scores = torch.where(mask[None, None], scores, -1e9)
        p = _softmax(scores, axis=-1)
        o = torch.einsum("bhqk,bhkd->bhqd", p, v)
        return (lambda x, *d: x.permute(*d))(o, 0, 2, 1, 3).reshape(B, S, D) @ wo

    def _B_ref(x, wqkv, wo):
        B, S, D = x.shape
        H = 32; Dh = D // H
        qkv = (lambda x, *d: x.permute(*d))((x @ wqkv).reshape(B, S, 3, H, Dh), 2, 0, 3, 1, 4)
        q, k, v = qkv[0], qkv[1], qkv[2]
        scale = Dh ** -0.5
        scores = torch.einsum("bhqd,bhkd->bhqk", q, k) * scale
        p = _softmax(scores, axis=-1)
        o = torch.einsum("bhqk,bhkd->bhqd", p, v)
        return (lambda x, *d: x.permute(*d))(o, 0, 2, 1, 3).reshape(B, S, D) @ wo

    x = A_x
    g = _sigmoid((x * gate_w).sum(-1, keepdims=True))
    a = _A_ref(x, A_wqkv, A_wo)
    b = _B_ref(x, B_wqkv, B_wo)
    return g * a + (1 - g) * b
```

```cpp
#include <cuda_runtime.h>
#include <cuda_bf16.h>
#include <cuda.h>
#include <stdint.h>

#define SEQ 2048
#define DM 512
#define NH 32

__device__ __align__(1024) __nv_bfloat16 g_qkv[2 * 3 * NH * SEQ * 16];
__device__ __align__(1024) __nv_bfloat16 g_ocat[SEQ * 1024];
__device__ float g_gate[SEQ];

__device__ __forceinline__ uint32_t smem_u32(const void* p) { return (uint32_t)__cvta_generic_to_shared(p); }
__device__ __forceinline__ void mbar_init(uint32_t bar, uint32_t count) {
  asm volatile("mbarrier.init.shared::cta.b64 [%0], %1;" ::"r"(bar), "r"(count) : "memory");
}
__device__ __forceinline__ void mbar_expect_tx(uint32_t bar, uint32_t bytes) {
  asm volatile("mbarrier.arrive.expect_tx.shared::cta.b64 _, [%0], %1;" ::"r"(bar), "r"(bytes) : "memory");
}
__device__ __forceinline__ void mbar_arrive(uint32_t bar) {
  asm volatile("mbarrier.arrive.shared::cta.b64 _, [%0];" ::"r"(bar) : "memory");
}
__device__ __forceinline__ void mbar_wait(uint32_t bar, uint32_t parity) {
  uint32_t done = 0;
#pragma unroll 1
  for (uint32_t it = 0; it < (1u << 22); ++it) {
    asm volatile(
        "{\n.reg .pred p;\n"
        "mbarrier.try_wait.parity.shared::cta.b64 p, [%1], %2;\n"
        "selp.u32 %0, 1, 0, p;\n}\n"
        : "=r"(done)
        : "r"(bar), "r"(parity)
        : "memory");
    if (done) return;
  }
  __trap();
}
__device__ __forceinline__ void fence_barrier_init() {
  asm volatile("fence.mbarrier_init.release.cluster;" ::: "memory");
}
__device__ __forceinline__ void fence_proxy_async() { asm volatile("fence.proxy.async.shared::cta;" ::: "memory"); }
__device__ __forceinline__ void tma_load_2d(uint32_t dst, const CUtensorMap* tm, uint32_t bar, int c0, int c1) {
  asm volatile(
      "cp.async.bulk.tensor.2d.shared::cluster.global.mbarrier::complete_tx::bytes [%0], [%1, {%3, %4}], [%2];"
      ::"r"(dst), "l"((uint64_t)tm), "r"(bar), "r"(c0), "r"(c1)
      : "memory");
}
__device__ __forceinline__ void bulk_load(uint32_t dst, const void* src, uint32_t bytes, uint32_t bar) {
  asm volatile("cp.async.bulk.shared::cluster.global.mbarrier::complete_tx::bytes [%0], [%1], %2, [%3];"
               ::"r"(dst), "l"((uint64_t)src), "r"(bytes), "r"(bar)
               : "memory");
}
__device__ __forceinline__ void wgmma_fence() { asm volatile("wgmma.fence.sync.aligned;" ::: "memory"); }
__device__ __forceinline__ void wgmma_commit() { asm volatile("wgmma.commit_group.sync.aligned;" ::: "memory"); }
template <int N>
__device__ __forceinline__ void wgmma_wait() { asm volatile("wgmma.wait_group.sync.aligned %0;" ::"n"(N) : "memory"); }

__device__ __forceinline__ uint64_t make_desc(uint32_t addr, uint32_t lbo_bytes, uint32_t sbo_bytes, uint32_t swz) {
  uint64_t d = 0;
  d |= (uint64_t)((addr & 0x3FFFF) >> 4);
  d |= (uint64_t)((lbo_bytes >> 4) & 0x3FFF) << 16;
  d |= (uint64_t)((sbo_bytes >> 4) & 0x3FFF) << 32;
  d |= (uint64_t)swz << 62;
  return d;
}
__device__ __forceinline__ float ex2f(float x) {
  float y;
  asm("ex2.approx.ftz.f32 %0, %1;" : "=f"(y) : "f"(x));
  return y;
}
__device__ __forceinline__ uint32_t pack_bf16(float lo, float hi) {
  uint32_t r;
  asm("cvt.rn.bf16x2.f32 %0, %1, %2;" : "=r"(r) : "f"(hi), "f"(lo));
  return r;
}
__device__ __forceinline__ float bf16_round(float x) { return __bfloat162float(__float2bfloat16_rn(x)); }

__device__ __forceinline__ void wgmma_ss_n192_tb(float* d, uint64_t da, uint64_t db, int scaleD) {
  asm volatile("{\n.reg .pred p;\nsetp.ne.b32 p, %98, 0;\n"
    "wgmma.mma_async.sync.aligned.m64n192k16.f32.bf16.bf16 {%0, %1, %2, %3, %4, %5, %6, %7, %8, %9, %10, %11, %12, %13, %14, %15, %16, %17, %18, %19, %20, %21, %22, %23, %24, %25, %26, %27, %28, %29, %30, %31, %32, %33, %34, %35, %36, %37, %38, %39, %40, %41, %42, %43, %44, %45, %46, %47, %48, %49, %50, %51, %52, %53, %54, %55, %56, %57, %58, %59, %60, %61, %62, %63, %64, %65, %66, %67, %68, %69, %70, %71, %72, %73, %74, %75, %76, %77, %78, %79, %80, %81, %82, %83, %84, %85, %86, %87, %88, %89, %90, %91, %92, %93, %94, %95}, %96, %97, p, 1, 1, 0, 1;\n}\n"
    : "+f"(d[0]), "+f"(d[1]), "+f"(d[2]), "+f"(d[3]), "+f"(d[4]), "+f"(d[5]), "+f"(d[6]), "+f"(d[7]), "+f"(d[8]), "+f"(d[9]), "+f"(d[10]), "+f"(d[11]), "+f"(d[12]), "+f"(d[13]), "+f"(d[14]), "+f"(d[15]), "+f"(d[16]), "+f"(d[17]), "+f"(d[18]), "+f"(d[19]), "+f"(d[20]), "+f"(d[21]), "+f"(d[22]), "+f"(d[23]), "+f"(d[24]), "+f"(d[25]), "+f"(d[26]), "+f"(d[27]), "+f"(d[28]), "+f"(d[29]), "+f"(d[30]), "+f"(d[31]), "+f"(d[32]), "+f"(d[33]), "+f"(d[34]), "+f"(d[35]), "+f"(d[36]), "+f"(d[37]), "+f"(d[38]), "+f"(d[39]), "+f"(d[40]), "+f"(d[41]), "+f"(d[42]), "+f"(d[43]), "+f"(d[44]), "+f"(d[45]), "+f"(d[46]), "+f"(d[47]), "+f"(d[48]), "+f"(d[49]), "+f"(d[50]), "+f"(d[51]), "+f"(d[52]), "+f"(d[53]), "+f"(d[54]), "+f"(d[55]), "+f"(d[56]), "+f"(d[57]), "+f"(d[58]), "+f"(d[59]), "+f"(d[60]), "+f"(d[61]), "+f"(d[62]), "+f"(d[63]), "+f"(d[64]), "+f"(d[65]), "+f"(d[66]), "+f"(d[67]), "+f"(d[68]), "+f"(d[69]), "+f"(d[70]), "+f"(d[71]), "+f"(d[72]), "+f"(d[73]), "+f"(d[74]), "+f"(d[75]), "+f"(d[76]), "+f"(d[77]), "+f"(d[78]), "+f"(d[79]), "+f"(d[80]), "+f"(d[81]), "+f"(d[82]), "+f"(d[83]), "+f"(d[84]), "+f"(d[85]), "+f"(d[86]), "+f"(d[87]), "+f"(d[88]), "+f"(d[89]), "+f"(d[90]), "+f"(d[91]), "+f"(d[92]), "+f"(d[93]), "+f"(d[94]), "+f"(d[95])
    : "l"(da), "l"(db), "r"(scaleD));
}
__device__ __forceinline__ void wgmma_ss_n64_tb(float* d, uint64_t da, uint64_t db, int scaleD) {
  asm volatile("{\n.reg .pred p;\nsetp.ne.b32 p, %34, 0;\n"
    "wgmma.mma_async.sync.aligned.m64n64k16.f32.bf16.bf16 {%0, %1, %2, %3, %4, %5, %6, %7, %8, %9, %10, %11, %12, %13, %14, %15, %16, %17, %18, %19, %20, %21, %22, %23, %24, %25, %26, %27, %28, %29, %30, %31}, %32, %33, p, 1, 1, 0, 1;\n}\n"
    : "+f"(d[0]), "+f"(d[1]), "+f"(d[2]), "+f"(d[3]), "+f"(d[4]), "+f"(d[5]), "+f"(d[6]), "+f"(d[7]), "+f"(d[8]), "+f"(d[9]), "+f"(d[10]), "+f"(d[11]), "+f"(d[12]), "+f"(d[13]), "+f"(d[14]), "+f"(d[15]), "+f"(d[16]), "+f"(d[17]), "+f"(d[18]), "+f"(d[19]), "+f"(d[20]), "+f"(d[21]), "+f"(d[22]), "+f"(d[23]), "+f"(d[24]), "+f"(d[25]), "+f"(d[26]), "+f"(d[27]), "+f"(d[28]), "+f"(d[29]), "+f"(d[30]), "+f"(d[31])
    : "l"(da), "l"(db), "r"(scaleD));
}
__device__ __forceinline__ void wgmma_rs_n128(float* d, const uint32_t* a, uint64_t db, int scaleD) {
  asm volatile("{\n.reg .pred p;\nsetp.ne.b32 p, %69, 0;\n"
    "wgmma.mma_async.sync.aligned.m64n128k16.f32.bf16.bf16 {%0, %1, %2, %3, %4, %5, %6, %7, %8, %9, %10, %11, %12, %13, %14, %15, %16, %17, %18, %19, %20, %21, %22, %23, %24, %25, %26, %27, %28, %29, %30, %31, %32, %33, %34, %35, %36, %37, %38, %39, %40, %41, %42, %43, %44, %45, %46, %47, %48, %49, %50, %51, %52, %53, %54, %55, %56, %57, %58, %59, %60, %61, %62, %63}, {%64, %65, %66, %67}, %68, p, 1, 1, 0;\n}\n"
    : "+f"(d[0]), "+f"(d[1]), "+f"(d[2]), "+f"(d[3]), "+f"(d[4]), "+f"(d[5]), "+f"(d[6]), "+f"(d[7]), "+f"(d[8]), "+f"(d[9]), "+f"(d[10]), "+f"(d[11]), "+f"(d[12]), "+f"(d[13]), "+f"(d[14]), "+f"(d[15]), "+f"(d[16]), "+f"(d[17]), "+f"(d[18]), "+f"(d[19]), "+f"(d[20]), "+f"(d[21]), "+f"(d[22]), "+f"(d[23]), "+f"(d[24]), "+f"(d[25]), "+f"(d[26]), "+f"(d[27]), "+f"(d[28]), "+f"(d[29]), "+f"(d[30]), "+f"(d[31]), "+f"(d[32]), "+f"(d[33]), "+f"(d[34]), "+f"(d[35]), "+f"(d[36]), "+f"(d[37]), "+f"(d[38]), "+f"(d[39]), "+f"(d[40]), "+f"(d[41]), "+f"(d[42]), "+f"(d[43]), "+f"(d[44]), "+f"(d[45]), "+f"(d[46]), "+f"(d[47]), "+f"(d[48]), "+f"(d[49]), "+f"(d[50]), "+f"(d[51]), "+f"(d[52]), "+f"(d[53]), "+f"(d[54]), "+f"(d[55]), "+f"(d[56]), "+f"(d[57]), "+f"(d[58]), "+f"(d[59]), "+f"(d[60]), "+f"(d[61]), "+f"(d[62]), "+f"(d[63])
    : "r"(a[0]), "r"(a[1]), "r"(a[2]), "r"(a[3]), "l"(db), "r"(scaleD));
}
__device__ __forceinline__ void wgmma_rs_n64(float* d, const uint32_t* a, uint64_t db, int scaleD) {
  asm volatile("{\n.reg .pred p;\nsetp.ne.b32 p, %37, 0;\n"
    "wgmma.mma_async.sync.aligned.m64n64k16.f32.bf16.bf16 {%0, %1, %2, %3, %4, %5, %6, %7, %8, %9, %10, %11, %12, %13, %14, %15, %16, %17, %18, %19, %20, %21, %22, %23, %24, %25, %26, %27, %28, %29, %30, %31}, {%32, %33, %34, %35}, %36, p, 1, 1, 0;\n}\n"
    : "+f"(d[0]), "+f"(d[1]), "+f"(d[2]), "+f"(d[3]), "+f"(d[4]), "+f"(d[5]), "+f"(d[6]), "+f"(d[7]), "+f"(d[8]), "+f"(d[9]), "+f"(d[10]), "+f"(d[11]), "+f"(d[12]), "+f"(d[13]), "+f"(d[14]), "+f"(d[15]), "+f"(d[16]), "+f"(d[17]), "+f"(d[18]), "+f"(d[19]), "+f"(d[20]), "+f"(d[21]), "+f"(d[22]), "+f"(d[23]), "+f"(d[24]), "+f"(d[25]), "+f"(d[26]), "+f"(d[27]), "+f"(d[28]), "+f"(d[29]), "+f"(d[30]), "+f"(d[31])
    : "r"(a[0]), "r"(a[1]), "r"(a[2]), "r"(a[3]), "l"(db), "r"(scaleD));
}
__device__ __forceinline__ void wgmma_rs_n16_tb(float* d, const uint32_t* a, uint64_t db, int scaleD) {
  asm volatile("{\n.reg .pred p;\nsetp.ne.b32 p, %13, 0;\n"
    "wgmma.mma_async.sync.aligned.m64n16k16.f32.bf16.bf16 {%0, %1, %2, %3, %4, %5, %6, %7}, {%8, %9, %10, %11}, %12, p, 1, 1, 1;\n}\n"
    : "+f"(d[0]), "+f"(d[1]), "+f"(d[2]), "+f"(d[3]), "+f"(d[4]), "+f"(d[5]), "+f"(d[6]), "+f"(d[7])
    : "r"(a[0]), "r"(a[1]), "r"(a[2]), "r"(a[3]), "l"(db), "r"(scaleD));
}
__device__ __forceinline__ void wgmma_rs_n8_tb(float* d, const uint32_t* a, uint64_t db, int scaleD) {
  asm volatile("{\n.reg .pred p;\nsetp.ne.b32 p, %9, 0;\n"
    "wgmma.mma_async.sync.aligned.m64n8k16.f32.bf16.bf16 {%0, %1, %2, %3}, {%4, %5, %6, %7}, %8, p, 1, 1, 1;\n}\n"
    : "+f"(d[0]), "+f"(d[1]), "+f"(d[2]), "+f"(d[3])
    : "r"(a[0]), "r"(a[1]), "r"(a[2]), "r"(a[3]), "l"(db), "r"(scaleD));
}


template <int BM, int BN, int STAGES, int KSTEPS, int MODE>
__global__ void __launch_bounds__(BM * 2, 1)
gemm_kernel(const __grid_constant__ CUtensorMap tmA, const __grid_constant__ CUtensorMap tmB0,
            const __grid_constant__ CUtensorMap tmB1, const __nv_bfloat16* __restrict__ x,
            const __nv_bfloat16* __restrict__ gate_w, __nv_bfloat16* __restrict__ out) {
  constexpr int NWG = BM / 64;
  constexpr int A_BYTES = BM * 128;
  constexpr int B_BYTES = BN * 128;
  constexpr int STAGE_BYTES = A_BYTES + B_BYTES;
  extern __shared__ uint8_t smem_raw[];
  uint32_t sbase = (smem_u32(smem_raw) + 1023u) & ~1023u;
  uint32_t bar_full = sbase + STAGES * STAGE_BYTES;
  uint32_t bar_empty = bar_full + 8 * STAGES;

  const int tid = threadIdx.x;
  const int warp = tid >> 5, lane = tid & 31;
  const int nt = blockIdx.x, mt = blockIdx.y;

  if (tid == 0) {
    for (int s = 0; s < STAGES; ++s) {
      mbar_init(bar_full + 8 * s, 1);
      mbar_init(bar_empty + 8 * s, NWG * 4);
    }
    fence_barrier_init();
  }
  __syncthreads();

  auto issue_load = [&](int ks) {
    const int s = ks % STAGES;
    const uint32_t sa = sbase + s * STAGE_BYTES, sb = sa + A_BYTES;
    mbar_expect_tx(bar_full + 8 * s, STAGE_BYTES);
    tma_load_2d(sa, &tmA, bar_full + 8 * s, ks * 64, mt * BM);
    if (MODE == 0) {
      const CUtensorMap* tb = (nt < 8) ? &tmB0 : &tmB1;
      const int n0 = (nt & 7) * BN;
#pragma unroll
      for (int j = 0; j < BN / 64; ++j) tma_load_2d(sb + j * 8192, tb, bar_full + 8 * s, n0 + j * 64, ks * 64);
    } else {
      const CUtensorMap* tb = (ks < 8) ? &tmB0 : &tmB1;
#pragma unroll
      for (int j = 0; j < BN / 64; ++j)
        tma_load_2d(sb + j * 8192, tb, bar_full + 8 * s, nt * BN + j * 64, (ks & 7) * 64);
    }
  };
  if (tid == 0) {
    for (int ks = 0; ks < STAGES && ks < KSTEPS; ++ks) issue_load(ks);
  }

  if (MODE == 0) {
    const int row = mt * BM + nt * 16 + warp;
    float acc = 0.f;
#pragma unroll
    for (int i = 0; i < 2; ++i) {
      const uint4 xv = *reinterpret_cast<const uint4*>(x + (size_t)row * DM + i * 256 + lane * 8);
      const uint4 gv = *reinterpret_cast<const uint4*>(gate_w + i * 256 + lane * 8);
      const __nv_bfloat16* xp = reinterpret_cast<const __nv_bfloat16*>(&xv);
      const __nv_bfloat16* gp = reinterpret_cast<const __nv_bfloat16*>(&gv);
#pragma unroll
      for (int e = 0; e < 8; ++e) acc += bf16_round(__bfloat162float(xp[e]) * __bfloat162float(gp[e]));
    }
#pragma unroll
    for (int o = 16; o > 0; o >>= 1) acc += __shfl_xor_sync(0xffffffffu, acc, o);
    if (lane == 0) {
      const float z = bf16_round(acc);
      g_gate[row] = bf16_round(1.f / (1.f + __expf(-z)));
    }
  }

  const int wg = warp >> 2;
  float acc[BN / 2];
#pragma unroll
  for (int i = 0; i < BN / 2; ++i) acc[i] = 0.f;

  for (int ks = 0; ks < KSTEPS; ++ks) {
    const int s = ks % STAGES;
    mbar_wait(bar_full + 8 * s, (ks / STAGES) & 1);
    const uint32_t sa = sbase + s * STAGE_BYTES + wg * 8192, sb = sbase + s * STAGE_BYTES + A_BYTES;
    wgmma_fence();
#pragma unroll
    for (int kk = 0; kk < 4; ++kk) {
      const uint64_t da = make_desc(sa + kk * 32, 16, 1024, 1);
      const uint64_t db = make_desc(sb + kk * 2048, 8192, 1024, 1);
      if constexpr (BN == 192) wgmma_ss_n192_tb(acc, da, db, 1);
      else wgmma_ss_n64_tb(acc, da, db, 1);
    }
    wgmma_commit();
    if (ks > 0) {
      wgmma_wait<1>();
      if (lane == 0) mbar_arrive(bar_empty + 8 * ((ks - 1) % STAGES));
      if (tid == 0 && ks - 1 + STAGES < KSTEPS) {
        mbar_wait(bar_empty + 8 * ((ks - 1) % STAGES), ((ks - 1) / STAGES) & 1);
        issue_load(ks - 1 + STAGES);
      }
    }
  }
  wgmma_wait<0>();

  const int g = lane >> 2, t = lane & 3;
  const int row_base = mt * BM + wg * 64 + (warp & 3) * 16;
  if (MODE == 0) {
#pragma unroll
    for (int j = 0; j < BN / 8; ++j) {
      const int idx16 = nt * (BN / 16) + (j >> 1);
      __nv_bfloat16* p = g_qkv + (size_t)idx16 * (SEQ * 16) + (row_base >> 3) * 128 + (j & 1) * 64 + g * 8 + 2 * t;
      *reinterpret_cast<uint32_t*>(p) = pack_bf16(acc[4 * j + 0], acc[4 * j + 1]);
      *reinterpret_cast<uint32_t*>(p + 128) = pack_bf16(acc[4 * j + 2], acc[4 * j + 3]);
    }
  } else {
#pragma unroll
    for (int j = 0; j < BN / 8; ++j) {
      __nv_bfloat16* p = out + (size_t)(row_base + g) * DM + nt * BN + j * 8 + 2 * t;
      *reinterpret_cast<uint32_t*>(p) = pack_bf16(acc[4 * j + 0], acc[4 * j + 1]);
      *reinterpret_cast<uint32_t*>(p + 8 * DM) = pack_bf16(acc[4 * j + 2], acc[4 * j + 3]);
    }
  }
}

#define ATT_C 0.36067376022224085f
#define NEG_BIG (-1.0e30f)

template <int N, bool MASK>
__device__ __forceinline__ void attn_tile(float (&O)[8], float (&L)[4], float& m0, float& m1,
                                          const uint32_t (&qa)[4], uint32_t kaddr, uint32_t vaddr,
                                          uint32_t onesaddr, int delta0) {
  float S[N / 2];
  wgmma_fence();
  if constexpr (N == 128) wgmma_rs_n128(S, qa, make_desc(kaddr, 128, 256, 0), 0);
  else wgmma_rs_n64(S, qa, make_desc(kaddr, 128, 256, 0), 0);
  wgmma_commit();
  wgmma_wait<0>();

  if (MASK) {
#pragma unroll
    for (int j = 0; j < N / 8; ++j) {
      const int d = delta0 - 8 * j;
      S[4 * j + 0] = ((unsigned)(d) < 256u) ? S[4 * j + 0] : -INFINITY;
      S[4 * j + 1] = ((unsigned)(d - 1) < 256u) ? S[4 * j + 1] : -INFINITY;
      S[4 * j + 2] = ((unsigned)(d + 8) < 256u) ? S[4 * j + 2] : -INFINITY;
      S[4 * j + 3] = ((unsigned)(d + 7) < 256u) ? S[4 * j + 3] : -INFINITY;
    }
  }
  float mx0 = fmaxf(S[0], S[1]), mx1 = fmaxf(S[2], S[3]);
#pragma unroll
  for (int j = 1; j < N / 8; ++j) {
    mx0 = fmaxf(mx0, fmaxf(S[4 * j + 0], S[4 * j + 1]));
    mx1 = fmaxf(mx1, fmaxf(S[4 * j + 2], S[4 * j + 3]));
  }
  mx0 = fmaxf(mx0, __shfl_xor_sync(0xffffffffu, mx0, 1));
  mx1 = fmaxf(mx1, __shfl_xor_sync(0xffffffffu, mx1, 1));
  mx0 = fmaxf(mx0, __shfl_xor_sync(0xffffffffu, mx0, 2));
  mx1 = fmaxf(mx1, __shfl_xor_sync(0xffffffffu, mx1, 2));
  const float mn0 = fmaxf(m0, mx0), mn1 = fmaxf(m1, mx1);
  const float a0 = ex2f((m0 - mn0) * ATT_C), a1 = ex2f((m1 - mn1) * ATT_C);
  m0 = mn0;
  m1 = mn1;
  const float mc0 = mn0 * ATT_C, mc1 = mn1 * ATT_C;
  O[0] *= a0; O[1] *= a0; O[2] *= a1; O[3] *= a1;
  O[4] *= a0; O[5] *= a0; O[6] *= a1; O[7] *= a1;
  L[0] *= a0; L[1] *= a0; L[2] *= a1; L[3] *= a1;

  uint32_t P[N / 4];
#pragma unroll
  for (int j = 0; j < N / 8; ++j) {
    const float p0 = ex2f(fmaf(S[4 * j + 0], ATT_C, -mc0));
    const float p1 = ex2f(fmaf(S[4 * j + 1], ATT_C, -mc0));
    const float p2 = ex2f(fmaf(S[4 * j + 2], ATT_C, -mc1));
    const float p3 = ex2f(fmaf(S[4 * j + 3], ATT_C, -mc1));
    P[2 * j + 0] = pack_bf16(p0, p1);
    P[2 * j + 1] = pack_bf16(p2, p3);
  }
  wgmma_fence();
#pragma unroll
  for (int kk = 0; kk < N / 16; ++kk) {
    const uint32_t a[4] = {P[4 * kk + 0], P[4 * kk + 1], P[4 * kk + 2], P[4 * kk + 3]};
    wgmma_rs_n16_tb(O, a, make_desc(vaddr + kk * 512, 256, 128, 0), 1);
    wgmma_rs_n8_tb(L, a, make_desc(onesaddr, 128, 128, 0), 1);
  }
  wgmma_commit();
}

__device__ __forceinline__ void load_q(uint32_t (&qa)[4], int idx16, int row_base, int g, int t) {
  const __nv_bfloat16* p = g_qkv + (size_t)idx16 * (SEQ * 16) + (row_base >> 3) * 128 + g * 8 + 2 * t;
  qa[0] = *reinterpret_cast<const uint32_t*>(p);
  qa[1] = *reinterpret_cast<const uint32_t*>(p + 128);
  qa[2] = *reinterpret_cast<const uint32_t*>(p + 64);
  qa[3] = *reinterpret_cast<const uint32_t*>(p + 128 + 64);
}

__device__ __forceinline__ void store_o(const float (&O)[8], const float (&L)[4], int branch, int h, int row_base,
                                        int g, int t) {
  const int r0 = row_base + g, r1 = r0 + 8;
  float f0 = g_gate[r0], f1 = g_gate[r1];
  if (branch == 1) { f0 = bf16_round(1.f - f0); f1 = bf16_round(1.f - f1); }
  f0 /= L[0];
  f1 /= L[2];
  __nv_bfloat16* p0 = g_ocat + (size_t)r0 * 1024 + branch * 512 + h * 16 + 2 * t;
  __nv_bfloat16* p1 = p0 + 8 * 1024;
  *reinterpret_cast<uint32_t*>(p0) = pack_bf16(O[0] * f0, O[1] * f0);
  *reinterpret_cast<uint32_t*>(p1) = pack_bf16(O[2] * f1, O[3] * f1);
  *reinterpret_cast<uint32_t*>(p0 + 8) = pack_bf16(O[4] * f0, O[5] * f0);
  *reinterpret_cast<uint32_t*>(p1 + 8) = pack_bf16(O[6] * f1, O[7] * f1);
}

#define ATT_SMEM_KB 0
#define ATT_SMEM_VB 65536
#define ATT_SMEM_KA 131072
#define ATT_SMEM_VA (131072 + 24576)
#define ATT_SMEM_ONES (131072 + 49152)
#define ATT_SMEM_BARS (ATT_SMEM_ONES + 256)
#define ATT_SMEM_TOTAL (ATT_SMEM_BARS + 128 + 1024)

__global__ void __launch_bounds__(512, 1) attn_kernel() {
  extern __shared__ uint8_t smem_raw[];
  const uint32_t sbase = (smem_u32(smem_raw) + 1023u) & ~1023u;
  uint8_t* sgen = smem_raw + (sbase - smem_u32(smem_raw));
  const int tid = threadIdx.x, warp = tid >> 5, lane = tid & 31;
  const int wg = warp >> 2, g = lane >> 2, t = lane & 3;
  const int h = blockIdx.x >> 2, qd = blockIdx.x & 3;
  const int q0 = qd * 512;
  const uint32_t bars = sbase + ATT_SMEM_BARS;

  if (tid == 0) {
    for (int i = 0; i < 9; ++i) mbar_init(bars + 8 * i, 1);
    fence_barrier_init();
  }
  if (tid < 64) reinterpret_cast<uint32_t*>(sgen + ATT_SMEM_ONES)[tid] = 0x3F803F80u;
  fence_proxy_async();
  __syncthreads();

  if (tid == 0) {
    const int rs = (q0 == 0) ? 0 : q0 - 256;
    const uint32_t bytes = (uint32_t)(q0 + 512 - rs) * 32u;
    const uint32_t off = (uint32_t)(rs - (q0 - 256)) * 32u;
    mbar_expect_tx(bars + 64, 2 * bytes);
    bulk_load(sbase + ATT_SMEM_KA + off, g_qkv + (size_t)(32 + h) * (SEQ * 16) + (size_t)rs * 16, bytes, bars + 64);
    bulk_load(sbase + ATT_SMEM_VA + off, g_qkv + (size_t)(64 + h) * (SEQ * 16) + (size_t)rs * 16, bytes, bars + 64);
    for (int c = 0; c < 8; ++c) {
      mbar_expect_tx(bars + 8 * c, 16384);
      bulk_load(sbase + ATT_SMEM_KB + c * 8192, g_qkv + (size_t)(96 + 32 + h) * (SEQ * 16) + c * 4096, 8192, bars + 8 * c);
      bulk_load(sbase + ATT_SMEM_VB + c * 8192, g_qkv + (size_t)(96 + 64 + h) * (SEQ * 16) + c * 4096, 8192, bars + 8 * c);
    }
  }
  const uint32_t ones = sbase + ATT_SMEM_ONES;

  mbar_wait(bars + 64, 0);
#pragma unroll 1
  for (int it = 0; it < 2; ++it) {
    const int qb = wg + 4 * it;
    const int r0 = q0 + qb * 64;
    const int row_base = r0 + (warp & 3) * 16;
    uint32_t qa[4];
    load_q(qa, h, row_base, g, t);
    float O[8] = {0.f, 0.f, 0.f, 0.f, 0.f, 0.f, 0.f, 0.f}, L[4] = {0.f, 0.f, 0.f, 0.f};
    float m0 = NEG_BIG, m1 = NEG_BIG;
#pragma unroll 1
    for (int i = 0; i < 5; ++i) {
      const int key0 = r0 - 256 + 64 * i;
      if (key0 < 0) continue;
      const uint32_t loc = (uint32_t)(key0 - (q0 - 256)) * 32u;
      const int delta0 = row_base + g - key0 - 2 * t;
      if (i == 0 || i == 4)
        attn_tile<64, true>(O, L, m0, m1, qa, sbase + ATT_SMEM_KA + loc, sbase + ATT_SMEM_VA + loc, ones, delta0);
      else
        attn_tile<64, false>(O, L, m0, m1, qa, sbase + ATT_SMEM_KA + loc, sbase + ATT_SMEM_VA + loc, ones, delta0);
    }
    wgmma_wait<0>();
    store_o(O, L, 0, h, row_base, g, t);
  }

#pragma unroll 1
  for (int it = 0; it < 2; ++it) {
    const int qb = wg + 4 * it;
    const int row_base = q0 + qb * 64 + (warp & 3) * 16;
    uint32_t qa[4];
    load_q(qa, 96 + h, row_base, g, t);
    float O[8] = {0.f, 0.f, 0.f, 0.f, 0.f, 0.f, 0.f, 0.f}, L[4] = {0.f, 0.f, 0.f, 0.f};
    float m0 = NEG_BIG, m1 = NEG_BIG;
#pragma unroll 1
    for (int kt = 0; kt < 16; ++kt) {
      if (it == 0 && (kt & 1) == 0) mbar_wait(bars + 8 * (kt >> 1), 0);
      attn_tile<128, false>(O, L, m0, m1, qa, sbase + ATT_SMEM_KB + kt * 4096, sbase + ATT_SMEM_VB + kt * 4096, ones, 0);
    }
    wgmma_wait<0>();
    store_o(O, L, 1, h, row_base, g, t);
  }
}

typedef CUresult (*PFN_encodeTiled)(CUtensorMap*, CUtensorMapDataType, cuuint32_t, void*, const cuuint64_t*,
                                    const cuuint64_t*, const cuuint32_t*, const cuuint32_t*, CUtensorMapInterleave,
                                    CUtensorMapSwizzle, CUtensorMapL2promotion, CUtensorMapFloatOOBfill);

static void make_map_2d(PFN_encodeTiled enc, CUtensorMap* tm, const void* ptr, uint64_t inner, uint64_t outer,
                        uint32_t box_inner, uint32_t box_outer) {
  cuuint64_t dims[2] = {inner, outer};
  cuuint64_t strides[1] = {inner * 2};
  cuuint32_t box[2] = {box_inner, box_outer};
  cuuint32_t es[2] = {1, 1};
  enc(tm, CU_TENSOR_MAP_DATA_TYPE_BFLOAT16, 2, const_cast<void*>(ptr), dims, strides, box, es,
      CU_TENSOR_MAP_INTERLEAVE_NONE, CU_TENSOR_MAP_SWIZZLE_128B, CU_TENSOR_MAP_L2_PROMOTION_L2_128B,
      CU_TENSOR_MAP_FLOAT_OOB_FILL_NONE);
}

#define K1_BM 256
#define K1_BN 192
#define K1_ST 4
#define K3_BM 128
#define K3_BN 64
#define K3_ST 6

extern "C" void kernel_launch(void* const* d_in, const int* in_sizes, int n_in, void* d_out, int out_size) {
  const __nv_bfloat16* x = (const __nv_bfloat16*)d_in[0];
  const __nv_bfloat16* wqkvA = (const __nv_bfloat16*)d_in[1];
  const __nv_bfloat16* woA = (const __nv_bfloat16*)d_in[2];
  const __nv_bfloat16* wqkvB = (const __nv_bfloat16*)d_in[4];
  const __nv_bfloat16* woB = (const __nv_bfloat16*)d_in[5];
  const __nv_bfloat16* gate_w = (const __nv_bfloat16*)d_in[6];
  __nv_bfloat16* out = (__nv_bfloat16*)d_out;

  static PFN_encodeTiled enc = nullptr;
  static void* ocat_ptr = nullptr;
  constexpr int K1_SMEM = K1_ST * (K1_BM * 128 + K1_BN * 128) + 1024 + 128;
  constexpr int K3_SMEM = K3_ST * (K3_BM * 128 + K3_BN * 128) + 1024 + 128;
  if (!enc) {
    cudaDriverEntryPointQueryResult qres;
    void* fn = nullptr;
    cudaGetDriverEntryPoint("cuTensorMapEncodeTiled", &fn, cudaEnableDefault, &qres);
    enc = (PFN_encodeTiled)fn;
    cudaGetSymbolAddress(&ocat_ptr, g_ocat);
    cudaFuncSetAttribute(gemm_kernel<K1_BM, K1_BN, K1_ST, 8, 0>, cudaFuncAttributeMaxDynamicSharedMemorySize, K1_SMEM);
    cudaFuncSetAttribute(gemm_kernel<K3_BM, K3_BN, K3_ST, 16, 1>, cudaFuncAttributeMaxDynamicSharedMemorySize, K3_SMEM);
    cudaFuncSetAttribute(attn_kernel, cudaFuncAttributeMaxDynamicSharedMemorySize, ATT_SMEM_TOTAL);
  }
  CUtensorMap tmX, tmWA, tmWB, tmO, tmWoA, tmWoB;
  make_map_2d(enc, &tmX, x, DM, SEQ, 64, K1_BM);
  make_map_2d(enc, &tmWA, wqkvA, 3 * DM, DM, 64, 64);
  make_map_2d(enc, &tmWB, wqkvB, 3 * DM, DM, 64, 64);
  make_map_2d(enc, &tmO, ocat_ptr, 1024, SEQ, 64, K3_BM);
  make_map_2d(enc, &tmWoA, woA, DM, DM, 64, 64);
  make_map_2d(enc, &tmWoB, woB, DM, DM, 64, 64);

  gemm_kernel<K1_BM, K1_BN, K1_ST, 8, 0><<<dim3(16, SEQ / K1_BM), K1_BM * 2, K1_SMEM>>>(tmX, tmWA, tmWB, x, gate_w, out);
  attn_kernel<<<128, 512, ATT_SMEM_TOTAL>>>();
  gemm_kernel<K3_BM, K3_BN, K3_ST, 16, 1><<<dim3(DM / K3_BN, SEQ / K3_BM), K3_BM * 2, K3_SMEM>>>(tmO, tmWoA, tmWoB, x, gate_w, out);
}
```

```cpp
#include <cuda_runtime.h>
#include <cuda_bf16.h>
#include <cuda.h>
#include <stdint.h>

#define SEQ 2048
#define DM 512
#define NH 32

__device__ __align__(1024) __nv_bfloat16 g_qkv[2 * 3 * NH * SEQ * 16];
__device__ __align__(1024) __nv_bfloat16 g_ocat[SEQ * 1024];
__device__ float g_gate[SEQ];

__device__ __forceinline__ uint32_t smem_u32(const void* p) { return (uint32_t)__cvta_generic_to_shared(p); }
__device__ __forceinline__ void mbar_init(uint32_t bar, uint32_t count) {
  asm volatile("mbarrier.init.shared::cta.b64 [%0], %1;" ::"r"(bar), "r"(count) : "memory");
}
__device__ __forceinline__ void mbar_expect_tx(uint32_t bar, uint32_t bytes) {
  asm volatile("mbarrier.arrive.expect_tx.shared::cta.b64 _, [%0], %1;" ::"r"(bar), "r"(bytes) : "memory");
}
__device__ __forceinline__ void mbar_arrive(uint32_t bar) {
  asm volatile("mbarrier.arrive.shared::cta.b64 _, [%0];" ::"r"(bar) : "memory");
}
__device__ __forceinline__ void mbar_wait(uint32_t bar, uint32_t parity) {
  uint32_t done = 0;
#pragma unroll 1
  for (uint32_t it = 0; it < (1u << 22); ++it) {
    asm volatile(
        "{\n.reg .pred p;\n"
        "mbarrier.try_wait.parity.shared::cta.b64 p, [%1], %2;\n"
        "selp.u32 %0, 1, 0, p;\n}\n"
        : "=r"(done)
        : "r"(bar), "r"(parity)
        : "memory");
    if (done) return;
  }
  __trap();
}
__device__ __forceinline__ void fence_barrier_init() {
  asm volatile("fence.mbarrier_init.release.cluster;" ::: "memory");
}
__device__ __forceinline__ void fence_proxy_async() { asm volatile("fence.proxy.async.shared::cta;" ::: "memory"); }
__device__ __forceinline__ void tma_load_2d(uint32_t dst, const CUtensorMap* tm, uint32_t bar, int c0, int c1) {
  asm volatile(
      "cp.async.bulk.tensor.2d.shared::cluster.global.mbarrier::complete_tx::bytes [%0], [%1, {%3, %4}], [%2];"
      ::"r"(dst), "l"((uint64_t)tm), "r"(bar), "r"(c0), "r"(c1)
      : "memory");
}
__device__ __forceinline__ void bulk_load(uint32_t dst, const void* src, uint32_t bytes, uint32_t bar) {
  asm volatile("cp.async.bulk.shared::cluster.global.mbarrier::complete_tx::bytes [%0], [%1], %2, [%3];"
               ::"r"(dst), "l"((uint64_t)src), "r"(bytes), "r"(bar)
               : "memory");
}
__device__ __forceinline__ void wgmma_fence() { asm volatile("wgmma.fence.sync.aligned;" ::: "memory"); }
__device__ __forceinline__ void wgmma_commit() { asm volatile("wgmma.commit_group.sync.aligned;" ::: "memory"); }
template <int N>
__device__ __forceinline__ void wgmma_wait() { asm volatile("wgmma.wait_group.sync.aligned %0;" ::"n"(N) : "memory"); }

__device__ __forceinline__ uint64_t make_desc(uint32_t addr, uint32_t lbo_bytes, uint32_t sbo_bytes, uint32_t swz) {
  uint64_t d = 0;
  d |= (uint64_t)((addr & 0x3FFFF) >> 4);
  d |= (uint64_t)((lbo_bytes >> 4) & 0x3FFF) << 16;
  d |= (uint64_t)((sbo_bytes >> 4) & 0x3FFF) << 32;
  d |= (uint64_t)swz << 62;
  return d;
}
__device__ __forceinline__ float ex2f(float x) {
  float y;
  asm("ex2.approx.ftz.f32 %0, %1;" : "=f"(y) : "f"(x));
  return y;
}
__device__ __forceinline__ uint32_t pack_bf16(float lo, float hi) {
  uint32_t r;
  asm("cvt.rn.bf16x2.f32 %0, %1, %2;" : "=r"(r) : "f"(hi), "f"(lo));
  return r;
}
__device__ __forceinline__ float bf16_round(float x) { return __bfloat162float(__float2bfloat16_rn(x)); }

__device__ __forceinline__ void wgmma_ss_n192_tb(float* d, uint64_t da, uint64_t db, int scaleD) {
  asm volatile("{\n.reg .pred p;\nsetp.ne.b32 p, %98, 0;\n"
    "wgmma.mma_async.sync.aligned.m64n192k16.f32.bf16.bf16 {%0, %1, %2, %3, %4, %5, %6, %7, %8, %9, %10, %11, %12, %13, %14, %15, %16, %17, %18, %19, %20, %21, %22, %23, %24, %25, %26, %27, %28, %29, %30, %31, %32, %33, %34, %35, %36, %37, %38, %39, %40, %41, %42, %43, %44, %45, %46, %47, %48, %49, %50, %51, %52, %53, %54, %55, %56, %57, %58, %59, %60, %61, %62, %63, %64, %65, %66, %67, %68, %69, %70, %71, %72, %73, %74, %75, %76, %77, %78, %79, %80, %81, %82, %83, %84, %85, %86, %87, %88, %89, %90, %91, %92, %93, %94, %95}, %96, %97, p, 1, 1, 0, 1;\n}\n"
    : "+f"(d[0]), "+f"(d[1]), "+f"(d[2]), "+f"(d[3]), "+f"(d[4]), "+f"(d[5]), "+f"(d[6]), "+f"(d[7]), "+f"(d[8]), "+f"(d[9]), "+f"(d[10]), "+f"(d[11]), "+f"(d[12]), "+f"(d[13]), "+f"(d[14]), "+f"(d[15]), "+f"(d[16]), "+f"(d[17]), "+f"(d[18]), "+f"(d[19]), "+f"(d[20]), "+f"(d[21]), "+f"(d[22]), "+f"(d[23]), "+f"(d[24]), "+f"(d[25]), "+f"(d[26]), "+f"(d[27]), "+f"(d[28]), "+f"(d[29]), "+f"(d[30]), "+f"(d[31]), "+f"(d[32]), "+f"(d[33]), "+f"(d[34]), "+f"(d[35]), "+f"(d[36]), "+f"(d[37]), "+f"(d[38]), "+f"(d[39]), "+f"(d[40]), "+f"(d[41]), "+f"(d[42]), "+f"(d[43]), "+f"(d[44]), "+f"(d[45]), "+f"(d[46]), "+f"(d[47]), "+f"(d[48]), "+f"(d[49]), "+f"(d[50]), "+f"(d[51]), "+f"(d[52]), "+f"(d[53]), "+f"(d[54]), "+f"(d[55]), "+f"(d[56]), "+f"(d[57]), "+f"(d[58]), "+f"(d[59]), "+f"(d[60]), "+f"(d[61]), "+f"(d[62]), "+f"(d[63]), "+f"(d[64]), "+f"(d[65]), "+f"(d[66]), "+f"(d[67]), "+f"(d[68]), "+f"(d[69]), "+f"(d[70]), "+f"(d[71]), "+f"(d[72]), "+f"(d[73]), "+f"(d[74]), "+f"(d[75]), "+f"(d[76]), "+f"(d[77]), "+f"(d[78]), "+f"(d[79]), "+f"(d[80]), "+f"(d[81]), "+f"(d[82]), "+f"(d[83]), "+f"(d[84]), "+f"(d[85]), "+f"(d[86]), "+f"(d[87]), "+f"(d[88]), "+f"(d[89]), "+f"(d[90]), "+f"(d[91]), "+f"(d[92]), "+f"(d[93]), "+f"(d[94]), "+f"(d[95])
    : "l"(da), "l"(db), "r"(scaleD));
}
__device__ __forceinline__ void wgmma_ss_n64_tb(float* d, uint64_t da, uint64_t db, int scaleD) {
  asm volatile("{\n.reg .pred p;\nsetp.ne.b32 p, %34, 0;\n"
    "wgmma.mma_async.sync.aligned.m64n64k16.f32.bf16.bf16 {%0, %1, %2, %3, %4, %5, %6, %7, %8, %9, %10, %11, %12, %13, %14, %15, %16, %17, %18, %19, %20, %21, %22, %23, %24, %25, %26, %27, %28, %29, %30, %31}, %32, %33, p, 1, 1, 0, 1;\n}\n"
    : "+f"(d[0]), "+f"(d[1]), "+f"(d[2]), "+f"(d[3]), "+f"(d[4]), "+f"(d[5]), "+f"(d[6]), "+f"(d[7]), "+f"(d[8]), "+f"(d[9]), "+f"(d[10]), "+f"(d[11]), "+f"(d[12]), "+f"(d[13]), "+f"(d[14]), "+f"(d[15]), "+f"(d[16]), "+f"(d[17]), "+f"(d[18]), "+f"(d[19]), "+f"(d[20]), "+f"(d[21]), "+f"(d[22]), "+f"(d[23]), "+f"(d[24]), "+f"(d[25]), "+f"(d[26]), "+f"(d[27]), "+f"(d[28]), "+f"(d[29]), "+f"(d[30]), "+f"(d[31])
    : "l"(da), "l"(db), "r"(scaleD));
}
__device__ __forceinline__ void wgmma_ss_n128_tb(float* d, uint64_t da, uint64_t db, int scaleD) {
  asm volatile("{\n.reg .pred p;\nsetp.ne.b32 p, %66, 0;\n"
    "wgmma.mma_async.sync.aligned.m64n128k16.f32.bf16.bf16 {%0, %1, %2, %3, %4, %5, %6, %7, %8, %9, %10, %11, %12, %13, %14, %15, %16, %17, %18, %19, %20, %21, %22, %23, %24, %25, %26, %27, %28, %29, %30, %31, %32, %33, %34, %35, %36, %37, %38, %39, %40, %41, %42, %43, %44, %45, %46, %47, %48, %49, %50, %51, %52, %53, %54, %55, %56, %57, %58, %59, %60, %61, %62, %63}, %64, %65, p, 1, 1, 0, 1;\n}\n"
    : "+f"(d[0]), "+f"(d[1]), "+f"(d[2]), "+f"(d[3]), "+f"(d[4]), "+f"(d[5]), "+f"(d[6]), "+f"(d[7]), "+f"(d[8]), "+f"(d[9]), "+f"(d[10]), "+f"(d[11]), "+f"(d[12]), "+f"(d[13]), "+f"(d[14]), "+f"(d[15]), "+f"(d[16]), "+f"(d[17]), "+f"(d[18]), "+f"(d[19]), "+f"(d[20]), "+f"(d[21]), "+f"(d[22]), "+f"(d[23]), "+f"(d[24]), "+f"(d[25]), "+f"(d[26]), "+f"(d[27]), "+f"(d[28]), "+f"(d[29]), "+f"(d[30]), "+f"(d[31]), "+f"(d[32]), "+f"(d[33]), "+f"(d[34]), "+f"(d[35]), "+f"(d[36]), "+f"(d[37]), "+f"(d[38]), "+f"(d[39]), "+f"(d[40]), "+f"(d[41]), "+f"(d[42]), "+f"(d[43]), "+f"(d[44]), "+f"(d[45]), "+f"(d[46]), "+f"(d[47]), "+f"(d[48]), "+f"(d[49]), "+f"(d[50]), "+f"(d[51]), "+f"(d[52]), "+f"(d[53]), "+f"(d[54]), "+f"(d[55]), "+f"(d[56]), "+f"(d[57]), "+f"(d[58]), "+f"(d[59]), "+f"(d[60]), "+f"(d[61]), "+f"(d[62]), "+f"(d[63])
    : "l"(da), "l"(db), "r"(scaleD));
}
__device__ __forceinline__ void wgmma_rs_n128(float* d, const uint32_t* a, uint64_t db, int scaleD) {
  asm volatile("{\n.reg .pred p;\nsetp.ne.b32 p, %69, 0;\n"
    "wgmma.mma_async.sync.aligned.m64n128k16.f32.bf16.bf16 {%0, %1, %2, %3, %4, %5, %6, %7, %8, %9, %10, %11, %12, %13, %14, %15, %16, %17, %18, %19, %20, %21, %22, %23, %24, %25, %26, %27, %28, %29, %30, %31, %32, %33, %34, %35, %36, %37, %38, %39, %40, %41, %42, %43, %44, %45, %46, %47, %48, %49, %50, %51, %52, %53, %54, %55, %56, %57, %58, %59, %60, %61, %62, %63}, {%64, %65, %66, %67}, %68, p, 1, 1, 0;\n}\n"
    : "+f"(d[0]), "+f"(d[1]), "+f"(d[2]), "+f"(d[3]), "+f"(d[4]), "+f"(d[5]), "+f"(d[6]), "+f"(d[7]), "+f"(d[8]), "+f"(d[9]), "+f"(d[10]), "+f"(d[11]), "+f"(d[12]), "+f"(d[13]), "+f"(d[14]), "+f"(d[15]), "+f"(d[16]), "+f"(d[17]), "+f"(d[18]), "+f"(d[19]), "+f"(d[20]), "+f"(d[21]), "+f"(d[22]), "+f"(d[23]), "+f"(d[24]), "+f"(d[25]), "+f"(d[26]), "+f"(d[27]), "+f"(d[28]), "+f"(d[29]), "+f"(d[30]), "+f"(d[31]), "+f"(d[32]), "+f"(d[33]), "+f"(d[34]), "+f"(d[35]), "+f"(d[36]), "+f"(d[37]), "+f"(d[38]), "+f"(d[39]), "+f"(d[40]), "+f"(d[41]), "+f"(d[42]), "+f"(d[43]), "+f"(d[44]), "+f"(d[45]), "+f"(d[46]), "+f"(d[47]), "+f"(d[48]), "+f"(d[49]), "+f"(d[50]), "+f"(d[51]), "+f"(d[52]), "+f"(d[53]), "+f"(d[54]), "+f"(d[55]), "+f"(d[56]), "+f"(d[57]), "+f"(d[58]), "+f"(d[59]), "+f"(d[60]), "+f"(d[61]), "+f"(d[62]), "+f"(d[63])
    : "r"(a[0]), "r"(a[1]), "r"(a[2]), "r"(a[3]), "l"(db), "r"(scaleD));
}
__device__ __forceinline__ void wgmma_rs_n64(float* d, const uint32_t* a, uint64_t db, int scaleD) {
  asm volatile("{\n.reg .pred p;\nsetp.ne.b32 p, %37, 0;\n"
    "wgmma.mma_async.sync.aligned.m64n64k16.f32.bf16.bf16 {%0, %1, %2, %3, %4, %5, %6, %7, %8, %9, %10, %11, %12, %13, %14, %15, %16, %17, %18, %19, %20, %21, %22, %23, %24, %25, %26, %27, %28, %29, %30, %31}, {%32, %33, %34, %35}, %36, p, 1, 1, 0;\n}\n"
    : "+f"(d[0]), "+f"(d[1]), "+f"(d[2]), "+f"(d[3]), "+f"(d[4]), "+f"(d[5]), "+f"(d[6]), "+f"(d[7]), "+f"(d[8]), "+f"(d[9]), "+f"(d[10]), "+f"(d[11]), "+f"(d[12]), "+f"(d[13]), "+f"(d[14]), "+f"(d[15]), "+f"(d[16]), "+f"(d[17]), "+f"(d[18]), "+f"(d[19]), "+f"(d[20]), "+f"(d[21]), "+f"(d[22]), "+f"(d[23]), "+f"(d[24]), "+f"(d[25]), "+f"(d[26]), "+f"(d[27]), "+f"(d[28]), "+f"(d[29]), "+f"(d[30]), "+f"(d[31])
    : "r"(a[0]), "r"(a[1]), "r"(a[2]), "r"(a[3]), "l"(db), "r"(scaleD));
}
__device__ __forceinline__ void wgmma_rs_n24_tb(float* d, const uint32_t* a, uint64_t db, int scaleD) {
  asm volatile("{\n.reg .pred p;\nsetp.ne.b32 p, %17, 0;\n"
    "wgmma.mma_async.sync.aligned.m64n24k16.f32.bf16.bf16 {%0, %1, %2, %3, %4, %5, %6, %7, %8, %9, %10, %11}, {%12, %13, %14, %15}, %16, p, 1, 1, 1;\n}\n"
    : "+f"(d[0]), "+f"(d[1]), "+f"(d[2]), "+f"(d[3]), "+f"(d[4]), "+f"(d[5]), "+f"(d[6]), "+f"(d[7]), "+f"(d[8]), "+f"(d[9]), "+f"(d[10]), "+f"(d[11])
    : "r"(a[0]), "r"(a[1]), "r"(a[2]), "r"(a[3]), "l"(db), "r"(scaleD));
}

template <int BM, int BN, int STAGES, int KSTEPS, int MODE>
__global__ void __launch_bounds__(BM * 2, 1)
gemm_kernel(const __grid_constant__ CUtensorMap tmA, const __grid_constant__ CUtensorMap tmB0,
            const __grid_constant__ CUtensorMap tmB1, const __nv_bfloat16* __restrict__ x,
            const __nv_bfloat16* __restrict__ gate_w, __nv_bfloat16* __restrict__ out) {
  constexpr int NWG = BM / 64;
  constexpr int A_BYTES = BM * 128;
  constexpr int B_BYTES = BN * 128;
  constexpr int STAGE_BYTES = A_BYTES + B_BYTES;
  extern __shared__ uint8_t smem_raw[];
  uint32_t sbase = (smem_u32(smem_raw) + 1023u) & ~1023u;
  uint32_t bar_full = sbase + STAGES * STAGE_BYTES;
  uint32_t bar_empty = bar_full + 8 * STAGES;

  const int tid = threadIdx.x;
  const int warp = tid >> 5, lane = tid & 31;
  const int nt = blockIdx.x, mt = blockIdx.y;

  if (tid == 0) {
    for (int s = 0; s < STAGES; ++s) {
      mbar_init(bar_full + 8 * s, 1);
      mbar_init(bar_empty + 8 * s, NWG * 4);
    }
    fence_barrier_init();
  }
  __syncthreads();

  auto issue_load = [&](int ks) {
    const int s = ks % STAGES;
    const uint32_t sa = sbase + s * STAGE_BYTES, sb = sa + A_BYTES;
    mbar_expect_tx(bar_full + 8 * s, STAGE_BYTES);
    tma_load_2d(sa, &tmA, bar_full + 8 * s, ks * 64, mt * BM);
    if (MODE == 0) {
      const CUtensorMap* tb = (nt < 8) ? &tmB0 : &tmB1;
      const int n0 = (nt & 7) * BN;
#pragma unroll
      for (int j = 0; j < BN / 64; ++j) tma_load_2d(sb + j * 8192, tb, bar_full + 8 * s, n0 + j * 64, ks * 64);
    } else {
      const CUtensorMap* tb = (ks < 8) ? &tmB0 : &tmB1;
#pragma unroll
      for (int j = 0; j < BN / 64; ++j)
        tma_load_2d(sb + j * 8192, tb, bar_full + 8 * s, nt * BN + j * 64, (ks & 7) * 64);
    }
  };
  if (tid == 0) {
    for (int ks = 0; ks < STAGES && ks < KSTEPS; ++ks) issue_load(ks);
  }

  if (MODE == 0) {
    const int row = mt * BM + nt * 16 + warp;
    float acc = 0.f;
#pragma unroll
    for (int i = 0; i < 2; ++i) {
      const uint4 xv = *reinterpret_cast<const uint4*>(x + (size_t)row * DM + i * 256 + lane * 8);
      const uint4 gv = *reinterpret_cast<const uint4*>(gate_w + i * 256 + lane * 8);
      const __nv_bfloat16* xp = reinterpret_cast<const __nv_bfloat16*>(&xv);
      const __nv_bfloat16* gp = reinterpret_cast<const __nv_bfloat16*>(&gv);
#pragma unroll
      for (int e = 0; e < 8; ++e) acc += bf16_round(__bfloat162float(xp[e]) * __bfloat162float(gp[e]));
    }
#pragma unroll
    for (int o = 16; o > 0; o >>= 1) acc += __shfl_xor_sync(0xffffffffu, acc, o);
    if (lane == 0) {
      const float z = bf16_round(acc);
      g_gate[row] = bf16_round(1.f / (1.f + __expf(-z)));
    }
  }

  const int wg = warp >> 2;
  float acc[BN / 2];
#pragma unroll
  for (int i = 0; i < BN / 2; ++i) acc[i] = 0.f;

  for (int ks = 0; ks < KSTEPS; ++ks) {
    const int s = ks % STAGES;
    mbar_wait(bar_full + 8 * s, (ks / STAGES) & 1);
    const uint32_t sa = sbase + s * STAGE_BYTES + wg * 8192, sb = sbase + s * STAGE_BYTES + A_BYTES;
    wgmma_fence();
#pragma unroll
    for (int kk = 0; kk < 4; ++kk) {
      const uint64_t da = make_desc(sa + kk * 32, 16, 1024, 1);
      const uint64_t db = make_desc(sb + kk * 2048, 8192, 1024, 1);
      if constexpr (BN == 192) wgmma_ss_n192_tb(acc, da, db, 1);
      else if constexpr (BN == 128) wgmma_ss_n128_tb(acc, da, db, 1);
      else wgmma_ss_n64_tb(acc, da, db, 1);
    }
    wgmma_commit();
    if (ks > 0) {
      wgmma_wait<1>();
      if (lane == 0) mbar_arrive(bar_empty + 8 * ((ks - 1) % STAGES));
      if (tid == 0 && ks - 1 + STAGES < KSTEPS) {
        mbar_wait(bar_empty + 8 * ((ks - 1) % STAGES), ((ks - 1) / STAGES) & 1);
        issue_load(ks - 1 + STAGES);
      }
    }
  }
  wgmma_wait<0>();

  const int g = lane >> 2, t = lane & 3;
  const int row_base = mt * BM + wg * 64 + (warp & 3) * 16;
  if (MODE == 0) {
#pragma unroll
    for (int j = 0; j < BN / 8; ++j) {
      const int idx16 = nt * (BN / 16) + (j >> 1);
      __nv_bfloat16* p = g_qkv + (size_t)idx16 * (SEQ * 16) + (row_base >> 3) * 128 + (j & 1) * 64 + g * 8 + 2 * t;
      *reinterpret_cast<uint32_t*>(p) = pack_bf16(acc[4 * j + 0], acc[4 * j + 1]);
      *reinterpret_cast<uint32_t*>(p + 128) = pack_bf16(acc[4 * j + 2], acc[4 * j + 3]);
    }
  } else {
#pragma unroll
    for (int j = 0; j < BN / 8; ++j) {
      __nv_bfloat16* p = out + (size_t)(row_base + g) * DM + nt * BN + j * 8 + 2 * t;
      *reinterpret_cast<uint32_t*>(p) = pack_bf16(acc[4 * j + 0], acc[4 * j + 1]);
      *reinterpret_cast<uint32_t*>(p + 8 * DM) = pack_bf16(acc[4 * j + 2], acc[4 * j + 3]);
    }
  }
}

#define ATT_C 0.36067376022224085f
#define NEG_BIG (-1.0e30f)
#define POLY_MASK 0x00

__device__ __forceinline__ void ldsm_x4(uint32_t& r0, uint32_t& r1, uint32_t& r2, uint32_t& r3, uint32_t addr) {
  asm volatile("ldmatrix.sync.aligned.m8n8.x4.shared.b16 {%0,%1,%2,%3}, [%4];"
               : "=r"(r0), "=r"(r1), "=r"(r2), "=r"(r3) : "r"(addr));
}
__device__ __forceinline__ void ldsm_x4_t(uint32_t& r0, uint32_t& r1, uint32_t& r2, uint32_t& r3, uint32_t addr) {
  asm volatile("ldmatrix.sync.aligned.m8n8.x4.trans.shared.b16 {%0,%1,%2,%3}, [%4];"
               : "=r"(r0), "=r"(r1), "=r"(r2), "=r"(r3) : "r"(addr));
}
__device__ __forceinline__ void mma16816(float* c, const uint32_t* a, uint32_t b0, uint32_t b1) {
  asm volatile("mma.sync.aligned.m16n8k16.row.col.f32.bf16.bf16.f32 {%0,%1,%2,%3}, {%4,%5,%6,%7}, {%8,%9}, {%0,%1,%2,%3};"
               : "+f"(c[0]), "+f"(c[1]), "+f"(c[2]), "+f"(c[3])
               : "r"(a[0]), "r"(a[1]), "r"(a[2]), "r"(a[3]), "r"(b0), "r"(b1));
}

__device__ __forceinline__ float ex2_poly(float s, float K1) {
  const float r = fmaf(s, ATT_C, K1);
  const float f = fmaf(s, ATT_C, K1 - r);
  float p = fmaf(0.009570099413394928f, f, 0.05591786280274391f);
  p = fmaf(p, f, 0.240247443318367f);
  p = fmaf(p, f, 0.6931217908859253f);
  p = fmaf(p, f, 0.9999992847442627f);
  const float rc = fmaxf(r, 12582912.f - 126.f);
  return __uint_as_float(__float_as_uint(p) + (__float_as_uint(rc) << 23));
}

template <int N, bool MASK>
__device__ __forceinline__ void warp_tile(float (&O)[12], float& m0, float& m1, const uint32_t (&qa)[4],
                                          uint32_t kaddr, uint32_t vaddr, int jrel0, int ia) {
  float S[N / 2];
#pragma unroll
  for (int i = 0; i < N / 2; ++i) S[i] = 0.f;
#pragma unroll
  for (int jb = 0; jb < N / 16; ++jb) {
    uint32_t b0, b1, b2, b3;
    ldsm_x4(b0, b1, b2, b3, kaddr + jb * 512);
    mma16816(&S[8 * jb], qa, b0, b1);
    mma16816(&S[8 * jb + 4], qa, b2, b3);
  }
  if (MASK) {
    const int lo0 = max(ia - 255, 0), lo1 = max(ia + 8 - 255, 0);
    const unsigned w0 = (unsigned)(ia - lo0), w1 = (unsigned)(ia + 8 - lo1);
#pragma unroll
    for (int j = 0; j < N / 8; ++j) {
      const int jj = jrel0 + 8 * j;
      S[4 * j + 0] = ((unsigned)(jj - lo0) <= w0) ? S[4 * j + 0] : -INFINITY;
      S[4 * j + 1] = ((unsigned)(jj + 1 - lo0) <= w0) ? S[4 * j + 1] : -INFINITY;
      S[4 * j + 2] = ((unsigned)(jj - lo1) <= w1) ? S[4 * j + 2] : -INFINITY;
      S[4 * j + 3] = ((unsigned)(jj + 1 - lo1) <= w1) ? S[4 * j + 3] : -INFINITY;
    }
  }
  float mx0 = fmaxf(S[0], S[1]), mx1 = fmaxf(S[2], S[3]);
#pragma unroll
  for (int j = 1; j < N / 8; ++j) {
    mx0 = fmaxf(mx0, fmaxf(S[4 * j + 0], S[4 * j + 1]));
    mx1 = fmaxf(mx1, fmaxf(S[4 * j + 2], S[4 * j + 3]));
  }
  mx0 = fmaxf(mx0, __shfl_xor_sync(0xffffffffu, mx0, 1));
  mx1 = fmaxf(mx1, __shfl_xor_sync(0xffffffffu, mx1, 1));
  mx0 = fmaxf(mx0, __shfl_xor_sync(0xffffffffu, mx0, 2));
  mx1 = fmaxf(mx1, __shfl_xor_sync(0xffffffffu, mx1, 2));
  const float mc0 = fmaxf(m0, (fmaf(mx0, ATT_C, 12582912.f) - 12582911.f)), mc1 = fmaxf(m1, (fmaf(mx1, ATT_C, 12582912.f) - 12582911.f));
  const float a0 = ex2f(m0 - mc0), a1 = ex2f(m1 - mc1);
  m0 = mc0;
  m1 = mc1;
  const float K10 = 12582912.f - mc0, K11 = 12582912.f - mc1;
  O[0] *= a0; O[1] *= a0; O[2] *= a1; O[3] *= a1;
  O[4] *= a0; O[5] *= a0; O[6] *= a1; O[7] *= a1;
  O[8] *= a0; O[9] *= a0; O[10] *= a1; O[11] *= a1;
#pragma unroll
  for (int kk = 0; kk < N / 16; ++kk) {
    uint32_t P[4];
#define EXPV(i, mc, K1) ((!MASK && ((POLY_MASK >> (i)) & 1)) ? ex2_poly(S[8 * kk + (i)], K1) : ex2f(fmaf(S[8 * kk + (i)], ATT_C, -(mc))))
    P[0] = pack_bf16(EXPV(0, mc0, K10), EXPV(1, mc0, K10));
    P[1] = pack_bf16(EXPV(2, mc1, K11), EXPV(3, mc1, K11));
    P[2] = pack_bf16(EXPV(4, mc0, K10), EXPV(5, mc0, K10));
    P[3] = pack_bf16(EXPV(6, mc1, K11), EXPV(7, mc1, K11));
    uint32_t v0, v1, v2, v3;
    ldsm_x4_t(v0, v1, v2, v3, vaddr + kk * 512);
    mma16816(&O[0], P, v0, v1);
    mma16816(&O[4], P, v2, v3);
    mma16816(&O[8], P, 0x3F803F80u, 0x3F803F80u);
  }
}

__device__ __forceinline__ void load_q(uint32_t (&qa)[4], int idx16, int row_base, int g, int t) {
  const __nv_bfloat16* p = g_qkv + (size_t)idx16 * (SEQ * 16) + (row_base >> 3) * 128 + g * 8 + 2 * t;
  qa[0] = *reinterpret_cast<const uint32_t*>(p);
  qa[1] = *reinterpret_cast<const uint32_t*>(p + 128);
  qa[2] = *reinterpret_cast<const uint32_t*>(p + 64);
  qa[3] = *reinterpret_cast<const uint32_t*>(p + 128 + 64);
}

__device__ __forceinline__ void store_o(const float (&O)[12], int branch, int h, int row_base, int g, int t) {
  const int r0 = row_base + g, r1 = r0 + 8;
  float f0 = g_gate[r0], f1 = g_gate[r1];
  if (branch == 1) { f0 = bf16_round(1.f - f0); f1 = bf16_round(1.f - f1); }
  f0 /= O[8];
  f1 /= O[10];
  __nv_bfloat16* p0 = g_ocat + (size_t)r0 * 1024 + branch * 512 + h * 16 + 2 * t;
  __nv_bfloat16* p1 = p0 + 8 * 1024;
  *reinterpret_cast<uint32_t*>(p0) = pack_bf16(O[0] * f0, O[1] * f0);
  *reinterpret_cast<uint32_t*>(p1) = pack_bf16(O[2] * f1, O[3] * f1);
  *reinterpret_cast<uint32_t*>(p0 + 8) = pack_bf16(O[4] * f0, O[5] * f0);
  *reinterpret_cast<uint32_t*>(p1 + 8) = pack_bf16(O[6] * f1, O[7] * f1);
}

#define ATT_SMEM_KB 0
#define ATT_SMEM_VB 65536
#define ATT_SMEM_KA 131072
#define ATT_SMEM_VA (ATT_SMEM_KA + 24576)
#define ATT_SMEM_BARS (ATT_SMEM_VA + 24576)
#define ATT_SMEM_TOTAL (ATT_SMEM_BARS + 128 + 1024)
#define ATT_THREADS 512

__global__ void __launch_bounds__(ATT_THREADS, 1) attn_kernel() {
  extern __shared__ uint8_t smem_raw[];
  const uint32_t sbase = (smem_u32(smem_raw) + 1023u) & ~1023u;
  uint8_t* sgen = smem_raw + (sbase - smem_u32(smem_raw));
  const int tid = threadIdx.x, warp = tid >> 5, lane = tid & 31;
  const int g = lane >> 2, t = lane & 3;
  const int h = blockIdx.x >> 2, qd = blockIdx.x & 3;
  const int q0 = qd * 512;
  const uint32_t bars = sbase + ATT_SMEM_BARS;

  if (tid == 0) {
    for (int i = 0; i < 9; ++i) mbar_init(bars + 8 * i, 1);
    fence_barrier_init();
  }
  if (q0 == 0) {
    uint4 z = make_uint4(0, 0, 0, 0);
    reinterpret_cast<uint4*>(sgen + ATT_SMEM_KA)[tid] = z;
    reinterpret_cast<uint4*>(sgen + ATT_SMEM_VA)[tid] = z;
  }
  __syncthreads();

  if (tid == 0) {
    const int rs = (q0 == 0) ? 0 : q0 - 256;
    const uint32_t bytes = (uint32_t)(q0 + 512 - rs) * 32u;
    const uint32_t off = (uint32_t)(rs - (q0 - 256)) * 32u;
    mbar_expect_tx(bars + 64, 2 * bytes);
    bulk_load(sbase + ATT_SMEM_KA + off, g_qkv + (size_t)(32 + h) * (SEQ * 16) + (size_t)rs * 16, bytes, bars + 64);
    bulk_load(sbase + ATT_SMEM_VA + off, g_qkv + (size_t)(64 + h) * (SEQ * 16) + (size_t)rs * 16, bytes, bars + 64);
    for (int c = 0; c < 8; ++c) {
      mbar_expect_tx(bars + 8 * c, 16384);
      bulk_load(sbase + ATT_SMEM_KB + c * 8192, g_qkv + (size_t)(96 + 32 + h) * (SEQ * 16) + c * 4096, 8192, bars + 8 * c);
      bulk_load(sbase + ATT_SMEM_VB + c * 8192, g_qkv + (size_t)(96 + 64 + h) * (SEQ * 16) + c * 4096, 8192, bars + 8 * c);
    }
  }
  const uint32_t koff = lane * 16;
  const uint32_t voff = ((lane >> 3) & 1) * 256 + (lane >> 4) * 128 + (lane & 7) * 16;

  mbar_wait(bars + 64, 0);
#pragma unroll 1
  for (int it = 0; it < 2; ++it) {
    const int r0 = q0 + (warp + 16 * it) * 16;
    uint32_t qa[4];
    load_q(qa, h, r0, g, t);
    float O[12];
#pragma unroll
    for (int i = 0; i < 12; ++i) O[i] = 0.f;
    float m0 = NEG_BIG, m1 = NEG_BIG;
    {
      const uint32_t loc = (uint32_t)(r0 - 256 - (q0 - 256)) * 32u;
      if (r0 - 256 + 128 > 0)
        warp_tile<128, true>(O, m0, m1, qa, sbase + ATT_SMEM_KA + loc + koff, sbase + ATT_SMEM_VA + loc + voff, r0 - 256 + 2 * t, r0 + g);
      warp_tile<144, true>(O, m0, m1, qa, sbase + ATT_SMEM_KA + loc + 4096 + koff, sbase + ATT_SMEM_VA + loc + 4096 + voff, r0 - 128 + 2 * t, r0 + g);
    }
    store_o(O, 0, h, r0, g, t);
  }

#pragma unroll 1
  for (int it = 0; it < 2; ++it) {
    const int r0 = q0 + (warp + 16 * it) * 16;
    uint32_t qa[4];
    load_q(qa, 96 + h, r0, g, t);
    float O[12];
#pragma unroll
    for (int i = 0; i < 12; ++i) O[i] = 0.f;
    float m0 = NEG_BIG, m1 = NEG_BIG;
#pragma unroll 1
    for (int kt = 0; kt < 16; ++kt) {
      if (it == 0 && (kt & 1) == 0) mbar_wait(bars + 8 * (kt >> 1), 0);
      warp_tile<128, false>(O, m0, m1, qa, sbase + ATT_SMEM_KB + kt * 4096 + koff, sbase + ATT_SMEM_VB + kt * 4096 + voff, 0, 0);
    }
    store_o(O, 1, h, r0, g, t);
  }
}

typedef CUresult (*PFN_encodeTiled)(CUtensorMap*, CUtensorMapDataType, cuuint32_t, void*, const cuuint64_t*,
                                    const cuuint64_t*, const cuuint32_t*, const cuuint32_t*, CUtensorMapInterleave,
                                    CUtensorMapSwizzle, CUtensorMapL2promotion, CUtensorMapFloatOOBfill);

static void make_map_2d(PFN_encodeTiled enc, CUtensorMap* tm, const void* ptr, uint64_t inner, uint64_t outer,
                        uint32_t box_inner, uint32_t box_outer) {
  cuuint64_t dims[2] = {inner, outer};
  cuuint64_t strides[1] = {inner * 2};
  cuuint32_t box[2] = {box_inner, box_outer};
  cuuint32_t es[2] = {1, 1};
  enc(tm, CU_TENSOR_MAP_DATA_TYPE_BFLOAT16, 2, const_cast<void*>(ptr), dims, strides, box, es,
      CU_TENSOR_MAP_INTERLEAVE_NONE, CU_TENSOR_MAP_SWIZZLE_128B, CU_TENSOR_MAP_L2_PROMOTION_L2_128B,
      CU_TENSOR_MAP_FLOAT_OOB_FILL_NONE);
}

#define K1_BM 256
#define K1_BN 192
#define K1_ST 4
#define K3_BM 128
#define K3_BN 64
#define K3_ST 6

extern "C" void kernel_launch(void* const* d_in, const int* in_sizes, int n_in, void* d_out, int out_size) {
  const __nv_bfloat16* x = (const __nv_bfloat16*)d_in[0];
  const __nv_bfloat16* wqkvA = (const __nv_bfloat16*)d_in[1];
  const __nv_bfloat16* woA = (const __nv_bfloat16*)d_in[2];
  const __nv_bfloat16* wqkvB = (const __nv_bfloat16*)d_in[4];
  const __nv_bfloat16* woB = (const __nv_bfloat16*)d_in[5];
  const __nv_bfloat16* gate_w = (const __nv_bfloat16*)d_in[6];
  __nv_bfloat16* out = (__nv_bfloat16*)d_out;

  static PFN_encodeTiled enc = nullptr;
  static void* ocat_ptr = nullptr;
  constexpr int K1_SMEM = K1_ST * (K1_BM * 128 + K1_BN * 128) + 1024 + 128;
  constexpr int K3_SMEM = K3_ST * (K3_BM * 128 + K3_BN * 128) + 1024 + 128;
  if (!enc) {
    cudaDriverEntryPointQueryResult qres;
    void* fn = nullptr;
    cudaGetDriverEntryPoint("cuTensorMapEncodeTiled", &fn, cudaEnableDefault, &qres);
    enc = (PFN_encodeTiled)fn;
    cudaGetSymbolAddress(&ocat_ptr, g_ocat);
    cudaFuncSetAttribute(gemm_kernel<K1_BM, K1_BN, K1_ST, 8, 0>, cudaFuncAttributeMaxDynamicSharedMemorySize, K1_SMEM);
    cudaFuncSetAttribute(gemm_kernel<K3_BM, K3_BN, K3_ST, 16, 1>, cudaFuncAttributeMaxDynamicSharedMemorySize, K3_SMEM);
    cudaFuncSetAttribute(attn_kernel, cudaFuncAttributeMaxDynamicSharedMemorySize, ATT_SMEM_TOTAL);
  }
  CUtensorMap tmX, tmWA, tmWB, tmO, tmWoA, tmWoB;
  make_map_2d(enc, &tmX, x, DM, SEQ, 64, K1_BM);
  make_map_2d(enc, &tmWA, wqkvA, 3 * DM, DM, 64, 64);
  make_map_2d(enc, &tmWB, wqkvB, 3 * DM, DM, 64, 64);
  make_map_2d(enc, &tmO, ocat_ptr, 1024, SEQ, 64, K3_BM);
  make_map_2d(enc, &tmWoA, woA, DM, DM, 64, 64);
  make_map_2d(enc, &tmWoB, woB, DM, DM, 64, 64);

  gemm_kernel<K1_BM, K1_BN, K1_ST, 8, 0><<<dim3(16, SEQ / K1_BM), K1_BM * 2, K1_SMEM>>>(tmX, tmWA, tmWB, x, gate_w, out);
  attn_kernel<<<128, ATT_THREADS, ATT_SMEM_TOTAL>>>();
  gemm_kernel<K3_BM, K3_BN, K3_ST, 16, 1><<<dim3(DM / K3_BN, SEQ / K3_BM), K3_BM * 2, K3_SMEM>>>(tmO, tmWoA, tmWoB, x, gate_w, out);
}
```
